```python
import torch

def _softmax(x, axis=-1):
    return torch.softmax(x, dim=axis)
def _gelu(x):
    return torch.nn.functional.gelu(x, approximate="tanh")
def _silu(x):
    return torch.nn.functional.silu(x)
def _sigmoid(x):
    return torch.sigmoid(x)
def _layernorm(x, axis=-1, eps=1e-5):
    m = x.mean(dim=axis, keepdim=True)
    v = x.var(dim=axis, keepdim=True, unbiased=False)
    return (x - m) / torch.sqrt(v + eps)
def _scatter_add(tgt, idx, src, axis=0):
    return tgt.clone().index_add_(axis, idx, src)
def _segment_sum(src, seg, n):
    out = torch.zeros((n,) + src.shape[1:], dtype=src.dtype)
    return out.index_add_(0, seg, src)
def _pad(x, pw):
    flat = tuple(v for pair in reversed(pw) for v in pair)
    return torch.nn.functional.pad(x, flat)

kernel_name = 'gated_mix__ssm_conv_s4d__ssm_conv_s5__prompt'

def setup_inputs():

    _w = (lambda a: (lambda t: t.to(torch.bfloat16) if t.is_floating_point() else t)(torch.as_tensor(a)))
    def _A_setup():
        Bsz, L, D, N = 1, 2048, 576, 128
        return {
            "u": _w((lambda *s: torch.randn(*s, dtype=torch.bfloat16) * 0.05)(Bsz, L, D)),
            "log_A_real": _w((lambda *s: torch.randn(*s, dtype=torch.bfloat16) * 3.2)(D, N) * 0.5),
            "A_imag": _w((lambda *s: torch.randn(*s, dtype=torch.bfloat16) * 0.05)(D, N) * 3.14),
            "C_real": _w((lambda *s: torch.randn(*s, dtype=torch.bfloat16) * 0.1)(D, N) / N ** 0.5),
            "C_imag": _w((lambda *s: torch.randn(*s, dtype=torch.bfloat16) * 0.1)(D, N) / N ** 0.5),
            "log_dt": _w((lambda *s: torch.randn(*s, dtype=torch.bfloat16) * 0.05)(D) * 0.5 - 4.0),
            "D_skip": _w((lambda *s: torch.randn(*s, dtype=torch.bfloat16) * 0.05)(D)),
        }
    _A_in = _A_setup()

    def _B_setup():
        B, S, D = 1, 2048, 576
        P = D
        Lambda_re = -0.5 * (lambda _x: torch.exp(torch.as_tensor(_x)))((lambda *s: torch.randn(*s, dtype=torch.bfloat16) * 0.2)(P))
        Lambda_im = (lambda *s: torch.randn(*s, dtype=torch.bfloat16) * 0.4)(P) * 1.0
        B_re = (lambda *s: torch.randn(*s, dtype=torch.bfloat16) * 0.2)(P, D) * (D ** -0.5)
        B_im = (lambda *s: torch.randn(*s, dtype=torch.bfloat16) * 0.2)(P, D) * (D ** -0.5)
        C_re = (lambda *s: torch.randn(*s, dtype=torch.bfloat16) * 0.2)(D, P) * (P ** -0.5)
        C_im = (lambda *s: torch.randn(*s, dtype=torch.bfloat16) * 0.2)(D, P) * (P ** -0.5)
        log_dt = (lambda *s: torch.randn(*s, dtype=torch.bfloat16) * 0.2)(P) * 0.3 - 2.0
        Dskip = (lambda *s: torch.randn(*s, dtype=torch.bfloat16) * 0.05)(D)
        return {
            "x": _w((lambda *s: torch.randn(*s, dtype=torch.bfloat16) * 0.05)(B, S, D)),
            "Lambda_re": _w(Lambda_re),
            "Lambda_im": _w(Lambda_im),
            "B_re": _w(B_re),
            "B_im": _w(B_im),
            "C_re": _w(C_re),
            "C_im": _w(C_im),
            "log_dt": _w(log_dt),
            "Dskip": _w(Dskip),
        }
    _B_in = _B_setup()

    return {
        "A_u": _A_in["u"],
        "A_log_A_real": _A_in["log_A_real"],
        "A_A_imag": _A_in["A_imag"],
        "A_C_real": _A_in["C_real"],
        "A_C_imag": _A_in["C_imag"],
        "A_log_dt": _A_in["log_dt"],
        "A_D_skip": _A_in["D_skip"],
        "B_x": _B_in["x"],
        "B_Lambda_re": _B_in["Lambda_re"],
        "B_Lambda_im": _B_in["Lambda_im"],
        "B_B_re": _B_in["B_re"],
        "B_B_im": _B_in["B_im"],
        "B_C_re": _B_in["C_re"],
        "B_C_im": _B_in["C_im"],
        "B_log_dt": _B_in["log_dt"],
        "B_Dskip": _B_in["Dskip"],
        "gate_w": _w((lambda *s: torch.randn(*s, dtype=torch.bfloat16) * 0.05)(576) * 16.0),
    }

def reference(A_u, A_log_A_real, A_A_imag, A_C_real, A_C_imag, A_log_dt, A_D_skip, B_x, B_Lambda_re, B_Lambda_im, B_B_re, B_B_im, B_C_re, B_C_im, B_log_dt, B_Dskip, gate_w):
    def _A_ref(u, log_A_real, A_imag, C_real, C_imag, log_dt, D_skip):
        L = u.shape[1]
        dt = torch.exp(log_dt)
        A = -torch.exp(log_A_real) + 1j * A_imag
        C = (C_real + 1j * C_imag) * dt[:, None]
        pos = (lambda x, dt: x.to(dt))(torch.arange(L), log_dt.dtype)
        P = torch.exp((A * dt[:, None])[:, :, None] * pos[None, None, :])
        K = 2.0 * torch.einsum("dn,dnl->dl", C, P).real
        L2 = 2 * L
        u_t = (lambda x, *d: x.permute(*d))(u, 0, 2, 1)
        Kf = (lambda x, *a, **k: torch.fft.rfft(x.float(), *a, **k))(K, L2)
        Uf = (lambda x, *a, **k: torch.fft.rfft(x.float(), *a, **k))(u_t, L2)
        y = (lambda x, *a, **k: torch.fft.irfft(x, *a, **k).to(torch.bfloat16))(Uf * Kf[None, :, :], L2)[:, :, :L]
        y = (lambda x, *d: x.permute(*d))(y, 0, 2, 1)
        return y + u * D_skip[None, None, :]

    def _B_ref(x, Lambda_re, Lambda_im, B_re, B_im, C_re, C_im, log_dt, Dskip):
        Bsz, L, H = x.shape
        Lam = Lambda_re + 1j * Lambda_im
        Bmat = B_re + 1j * B_im
        Cmat = C_re + 1j * C_im
        dt = torch.exp(log_dt)
        Lam_bar = torch.exp(dt * Lam)
        B_bar = ((Lam_bar - 1.0) / Lam)[:, None] * Bmat
        Bu = torch.einsum("bld,pd->blp", x + 0j, B_bar)
        h = torch.zeros_like(Bu[:, 0, :])
        hs = []
        for t in range(L):
            h = Lam_bar[None, :] * h + Bu[:, t, :]
            hs.append(h)
        hseq = torch.stack(hs, 1)
        y = 2.0 * torch.einsum("blp,dp->bld", hseq, Cmat).real + x * Dskip[None, None, :]
        return y

    x = A_u
    g = _sigmoid((x * gate_w).sum(-1, keepdims=True))
    a = _A_ref(x, A_log_A_real, A_A_imag, A_C_real, A_C_imag, A_log_dt, A_D_skip)
    b = _B_ref(x, B_Lambda_re, B_Lambda_im, B_B_re, B_B_im, B_C_re, B_C_im, B_log_dt, B_Dskip)
    return g * a + (1 - g) * b
```

```cpp
#include <cuda_runtime.h>
#include <cuda_bf16.h>
#include <cuda.h>
#include <stdint.h>

namespace {

constexpr int L_ = 2048, D_ = 576;
constexpr int NTHREADS = 512;
constexpr int N_S5 = 96, N_CONV = 36, N_CTA = N_S5 + N_CONV;

struct Scratch {
  alignas(1024) unsigned char H[16 * 18 * 16384];
  alignas(1024) __nv_bfloat16 y[576 * 2048];
  alignas(128) unsigned long long agg[16 * 576 * 2];
  alignas(128) unsigned long long gate[2048];
  alignas(128) unsigned hflag[16 * 18];
  alignas(128) unsigned ycnt[6 * 32];
  alignas(128) unsigned short kd[576 * 776];
  alignas(128) unsigned kflag[576];
  alignas(128) unsigned char uT[288 * 4496];
  alignas(128) unsigned epoch[132 * 32];
};
__device__ Scratch g_ws;

#define STAMP(i) do { } while (0)

struct Params {
  const __nv_bfloat16* u;
  const __nv_bfloat16* logA; const __nv_bfloat16* Aim; const __nv_bfloat16* Cre; const __nv_bfloat16* Cim;
  const __nv_bfloat16* logdtA; const __nv_bfloat16* DskA;
  const __nv_bfloat16* Lre; const __nv_bfloat16* Lim; const __nv_bfloat16* logdtB; const __nv_bfloat16* DskB;
  const __nv_bfloat16* gw;
  float* out;
  Scratch* ws;
  const uint32_t* lut;
  int swapB, swapC;
};

__device__ __forceinline__ uint32_t smem_u32(const void* p) { return (uint32_t)__cvta_generic_to_shared(p); }
__device__ __forceinline__ void mbar_init(uint32_t bar, int cnt) { asm volatile("mbarrier.init.shared::cta.b64 [%0], %1;" ::"r"(bar), "r"(cnt)); }
__device__ __forceinline__ void mbar_expect_tx(uint32_t bar, uint32_t bytes) { asm volatile("mbarrier.arrive.expect_tx.shared::cta.b64 _, [%0], %1;" ::"r"(bar), "r"(bytes) : "memory"); }
__device__ __forceinline__ void mbar_arrive(uint32_t bar) { asm volatile("mbarrier.arrive.shared::cta.b64 _, [%0];" ::"r"(bar) : "memory"); }
__device__ __forceinline__ void mbar_arrive_cluster(uint32_t cbar) { asm volatile("mbarrier.arrive.shared::cluster.b64 _, [%0];" ::"r"(cbar) : "memory"); }
__device__ __forceinline__ bool mbar_try(uint32_t bar, uint32_t parity) {
  uint32_t ok;
  asm volatile("{\n.reg .pred p;\nmbarrier.try_wait.parity.shared::cta.b64 p, [%1], %2;\nselp.u32 %0, 1, 0, p;\n}" : "=r"(ok) : "r"(bar), "r"(parity) : "memory");
  return ok != 0;
}
__device__ __noinline__ void spin_fail() { __trap(); }
__device__ __forceinline__ void mbar_wait(uint32_t bar, uint32_t parity) {
  if (mbar_try(bar, parity)) return;
  uint32_t n = 0;
  while (!mbar_try(bar, parity)) { if (++n > (1u << 22)) spin_fail(); }
}
__device__ __forceinline__ uint32_t mapa(uint32_t addr, uint32_t rank) { uint32_t r; asm("mapa.shared::cluster.u32 %0, %1, %2;" : "=r"(r) : "r"(addr), "r"(rank)); return r; }
__device__ __forceinline__ void fence_async_smem() { asm volatile("fence.proxy.async.shared::cta;" ::: "memory"); }
__device__ __forceinline__ void named_bar(int id, int n) { asm volatile("bar.sync %0, %1;" ::"r"(id), "r"(n) : "memory"); }

__device__ __forceinline__ void tma2d(uint32_t dst, const CUtensorMap* tm, uint32_t bar, int c0, int c1) {
  asm volatile("cp.async.bulk.tensor.2d.shared::cluster.global.mbarrier::complete_tx::bytes [%0], [%1, {%3,%4}], [%2];" ::"r"(dst), "l"(tm), "r"(bar), "r"(c0), "r"(c1) : "memory");
}
__device__ __forceinline__ void tma3d(uint32_t dst, const CUtensorMap* tm, uint32_t bar, int c0, int c1, int c2) {
  asm volatile("cp.async.bulk.tensor.3d.shared::cluster.global.mbarrier::complete_tx::bytes [%0], [%1, {%3,%4,%5}], [%2];" ::"r"(dst), "l"(tm), "r"(bar), "r"(c0), "r"(c1), "r"(c2) : "memory");
}
__device__ __forceinline__ void tma4d(uint32_t dst, const CUtensorMap* tm, uint32_t bar, int c0, int c1, int c2, int c3) {
  asm volatile("cp.async.bulk.tensor.4d.shared::cluster.global.mbarrier::complete_tx::bytes [%0], [%1, {%3,%4,%5,%6}], [%2];" ::"r"(dst), "l"(tm), "r"(bar), "r"(c0), "r"(c1), "r"(c2), "r"(c3) : "memory");
}
__device__ __forceinline__ void tma5d(uint32_t dst, const CUtensorMap* tm, uint32_t bar, int c0, int c1, int c2, int c3, int c4) {
  asm volatile("cp.async.bulk.tensor.5d.shared::cluster.global.mbarrier::complete_tx::bytes [%0], [%1, {%3,%4,%5,%6,%7}], [%2];" ::"r"(dst), "l"(tm), "r"(bar), "r"(c0), "r"(c1), "r"(c2), "r"(c3), "r"(c4) : "memory");
}
__device__ __forceinline__ void tma5d_mc(uint32_t dst, const CUtensorMap* tm, uint32_t bar, int c0, int c1, int c2, int c3, int c4, uint16_t mask) {
  asm volatile("cp.async.bulk.tensor.5d.shared::cluster.global.mbarrier::complete_tx::bytes.multicast::cluster [%0], [%1, {%3,%4,%5,%6,%7}], [%2], %8;" ::"r"(dst), "l"(tm), "r"(bar), "r"(c0), "r"(c1), "r"(c2), "r"(c3), "r"(c4), "h"(mask) : "memory");
}
__device__ __forceinline__ void bulk_g2s_mc(uint32_t dst, const void* src, uint32_t bytes, uint32_t bar, uint16_t mask) {
  asm volatile("cp.async.bulk.shared::cluster.global.mbarrier::complete_tx::bytes.multicast::cluster [%0], [%1], %2, [%3], %4;" ::"r"(dst), "l"(src), "r"(bytes), "r"(bar), "h"(mask) : "memory");
}
__device__ __forceinline__ void bulk_g2s(uint32_t dst, const void* src, uint32_t bytes, uint32_t bar) {
  asm volatile("cp.async.bulk.shared::cluster.global.mbarrier::complete_tx::bytes [%0], [%1], %2, [%3];" ::"r"(dst), "l"(src), "r"(bytes), "r"(bar) : "memory");
}
__device__ __forceinline__ void st_relaxed_u32(unsigned* p, unsigned v) { asm volatile("st.relaxed.gpu.global.u32 [%0], %1;" ::"l"(p), "r"(v) : "memory"); }
__device__ __forceinline__ void bulk_s2g(void* dst, uint32_t src, uint32_t bytes) {
  asm volatile("cp.async.bulk.global.shared::cta.bulk_group [%0], [%1], %2;" ::"l"(dst), "r"(src), "r"(bytes) : "memory");
}
__device__ __forceinline__ void bulk_commit() { asm volatile("cp.async.bulk.commit_group;" ::: "memory"); }
__device__ __forceinline__ void bulk_wait0() { asm volatile("cp.async.bulk.wait_group 0;" ::: "memory"); }

__device__ __forceinline__ void wg_fence() { asm volatile("wgmma.fence.sync.aligned;" ::: "memory"); }
__device__ __forceinline__ void wg_commit() { asm volatile("wgmma.commit_group.sync.aligned;" ::: "memory"); }
template <int N> __device__ __forceinline__ void wg_wait() { asm volatile("wgmma.wait_group.sync.aligned %0;" ::"n"(N) : "memory"); }
__device__ __forceinline__ uint64_t desc_sw128(uint32_t addr) { return (uint64_t)((addr & 0x3FFFF) >> 4) | ((uint64_t)1 << 16) | ((uint64_t)64 << 32) | ((uint64_t)1 << 62); }
__device__ __forceinline__ uint64_t desc_sw64(uint32_t addr) { return (uint64_t)((addr & 0x3FFFF) >> 4) | ((uint64_t)1 << 16) | ((uint64_t)32 << 32) | ((uint64_t)2 << 62); }

__device__ __forceinline__ void wgmma_ss_n128(float (&d)[64], uint64_t da, uint64_t db, int sd) {
  asm volatile("{\n.reg .pred p;\nsetp.ne.b32 p, %66, 0;\n"
    "wgmma.mma_async.sync.aligned.m64n128k16.f32.bf16.bf16 {%0, %1, %2, %3, %4, %5, %6, %7, %8, %9, %10, %11, %12, %13, %14, %15, %16, %17, %18, %19, %20, %21, %22, %23, %24, %25, %26, %27, %28, %29, %30, %31, %32, %33, %34, %35, %36, %37, %38, %39, %40, %41, %42, %43, %44, %45, %46, %47, %48, %49, %50, %51, %52, %53, %54, %55, %56, %57, %58, %59, %60, %61, %62, %63}, %64, %65, p, 1, 1, 0, 0;\n}\n"
    : "+f"(d[0]), "+f"(d[1]), "+f"(d[2]), "+f"(d[3]), "+f"(d[4]), "+f"(d[5]), "+f"(d[6]), "+f"(d[7]), "+f"(d[8]), "+f"(d[9]), "+f"(d[10]), "+f"(d[11]), "+f"(d[12]), "+f"(d[13]), "+f"(d[14]), "+f"(d[15]), "+f"(d[16]), "+f"(d[17]), "+f"(d[18]), "+f"(d[19]), "+f"(d[20]), "+f"(d[21]), "+f"(d[22]), "+f"(d[23]), "+f"(d[24]), "+f"(d[25]), "+f"(d[26]), "+f"(d[27]), "+f"(d[28]), "+f"(d[29]), "+f"(d[30]), "+f"(d[31]), "+f"(d[32]), "+f"(d[33]), "+f"(d[34]), "+f"(d[35]), "+f"(d[36]), "+f"(d[37]), "+f"(d[38]), "+f"(d[39]), "+f"(d[40]), "+f"(d[41]), "+f"(d[42]), "+f"(d[43]), "+f"(d[44]), "+f"(d[45]), "+f"(d[46]), "+f"(d[47]), "+f"(d[48]), "+f"(d[49]), "+f"(d[50]), "+f"(d[51]), "+f"(d[52]), "+f"(d[53]), "+f"(d[54]), "+f"(d[55]), "+f"(d[56]), "+f"(d[57]), "+f"(d[58]), "+f"(d[59]), "+f"(d[60]), "+f"(d[61]), "+f"(d[62]), "+f"(d[63])
    : "l"(da), "l"(db), "r"(sd));
}

__device__ __forceinline__ void wgmma_ss_n96(float (&d)[48], uint64_t da, uint64_t db, int sd) {
  asm volatile("{\n.reg .pred p;\nsetp.ne.b32 p, %50, 0;\n"
    "wgmma.mma_async.sync.aligned.m64n96k16.f32.bf16.bf16 {%0, %1, %2, %3, %4, %5, %6, %7, %8, %9, %10, %11, %12, %13, %14, %15, %16, %17, %18, %19, %20, %21, %22, %23, %24, %25, %26, %27, %28, %29, %30, %31, %32, %33, %34, %35, %36, %37, %38, %39, %40, %41, %42, %43, %44, %45, %46, %47}, %48, %49, p, 1, 1, 0, 0;\n}\n"
    : "+f"(d[0]), "+f"(d[1]), "+f"(d[2]), "+f"(d[3]), "+f"(d[4]), "+f"(d[5]), "+f"(d[6]), "+f"(d[7]), "+f"(d[8]), "+f"(d[9]), "+f"(d[10]), "+f"(d[11]), "+f"(d[12]), "+f"(d[13]), "+f"(d[14]), "+f"(d[15]), "+f"(d[16]), "+f"(d[17]), "+f"(d[18]), "+f"(d[19]), "+f"(d[20]), "+f"(d[21]), "+f"(d[22]), "+f"(d[23]), "+f"(d[24]), "+f"(d[25]), "+f"(d[26]), "+f"(d[27]), "+f"(d[28]), "+f"(d[29]), "+f"(d[30]), "+f"(d[31]), "+f"(d[32]), "+f"(d[33]), "+f"(d[34]), "+f"(d[35]), "+f"(d[36]), "+f"(d[37]), "+f"(d[38]), "+f"(d[39]), "+f"(d[40]), "+f"(d[41]), "+f"(d[42]), "+f"(d[43]), "+f"(d[44]), "+f"(d[45]), "+f"(d[46]), "+f"(d[47])
    : "l"(da), "l"(db), "r"(sd));
}

__device__ __forceinline__ void mma16816(float (&d)[4], uint32_t a0, uint32_t a1, uint32_t a2, uint32_t a3, uint32_t b0, uint32_t b1) {
  asm volatile("mma.sync.aligned.m16n8k16.row.col.f32.bf16.bf16.f32 {%0,%1,%2,%3}, {%4,%5,%6,%7}, {%8,%9}, {%0,%1,%2,%3};"
               : "+f"(d[0]), "+f"(d[1]), "+f"(d[2]), "+f"(d[3]) : "r"(a0), "r"(a1), "r"(a2), "r"(a3), "r"(b0), "r"(b1));
}
__device__ __forceinline__ void ldsm4(uint32_t (&r)[4], uint32_t addr) {
  asm volatile("ldmatrix.sync.aligned.m8n8.x4.shared.b16 {%0,%1,%2,%3}, [%4];" : "=r"(r[0]), "=r"(r[1]), "=r"(r[2]), "=r"(r[3]) : "r"(addr) : "memory");
}
__device__ __forceinline__ void ldsm4t(uint32_t (&r)[4], uint32_t addr) {
  asm volatile("ldmatrix.sync.aligned.m8n8.x4.trans.shared.b16 {%0,%1,%2,%3}, [%4];" : "=r"(r[0]), "=r"(r[1]), "=r"(r[2]), "=r"(r[3]) : "r"(addr) : "memory");
}
__device__ __forceinline__ void ldsm2(uint32_t& r0, uint32_t& r1, uint32_t addr) {
  asm volatile("ldmatrix.sync.aligned.m8n8.x2.shared.b16 {%0,%1}, [%2];" : "=r"(r0), "=r"(r1) : "r"(addr) : "memory");
}
__device__ __forceinline__ void stsm4t(uint32_t addr, uint32_t r0, uint32_t r1, uint32_t r2, uint32_t r3) {
  asm volatile("stmatrix.sync.aligned.m8n8.x4.trans.shared.b16 [%0], {%1,%2,%3,%4};" ::"r"(addr), "r"(r0), "r"(r1), "r"(r2), "r"(r3) : "memory");
}
__device__ __forceinline__ uint32_t lds32(uint32_t a) { uint32_t v; asm volatile("ld.shared.b32 %0, [%1];" : "=r"(v) : "r"(a) : "memory"); return v; }
__device__ __forceinline__ uint32_t lds16(uint32_t a) { uint16_t v; asm volatile("ld.shared.u16 %0, [%1];" : "=h"(v) : "r"(a) : "memory"); return v; }
__device__ __forceinline__ uint4 lds128(uint32_t a) { uint4 v; asm volatile("ld.shared.v4.b32 {%0,%1,%2,%3}, [%4];" : "=r"(v.x), "=r"(v.y), "=r"(v.z), "=r"(v.w) : "r"(a) : "memory"); return v; }
__device__ __forceinline__ void sts32(uint32_t a, uint32_t v) { asm volatile("st.shared.b32 [%0], %1;" ::"r"(a), "r"(v) : "memory"); }
__device__ __forceinline__ void sts16(uint32_t a, uint32_t v) { asm volatile("st.shared.u16 [%0], %1;" ::"r"(a), "h"((uint16_t)v) : "memory"); }
__device__ __forceinline__ void sts128(uint32_t a, uint4 v) { asm volatile("st.shared.v4.b32 [%0], {%1,%2,%3,%4};" ::"r"(a), "r"(v.x), "r"(v.y), "r"(v.z), "r"(v.w) : "memory"); }
__device__ __forceinline__ uint32_t pack_bf16(float lo, float hi) { uint32_t r; asm("cvt.rn.bf16x2.f32 %0, %1, %2;" : "=r"(r) : "f"(hi), "f"(lo)); return r; }
__device__ __forceinline__ float bf2f(__nv_bfloat16 v) { return __bfloat162float(v); }
__device__ __forceinline__ float bfround(float v) { return __bfloat162float(__float2bfloat16_rn(v)); }
__device__ __forceinline__ float bflo(uint32_t w) { return __uint_as_float(w << 16); }
__device__ __forceinline__ float bfhi(uint32_t w) { return __uint_as_float(w & 0xFFFF0000u); }
__device__ __forceinline__ uint32_t hmul2(uint32_t a, uint32_t b) { uint32_t r; asm("mul.rn.bf16x2 %0, %1, %2;" : "=r"(r) : "r"(a), "r"(b)); return r; }
__device__ __forceinline__ uint32_t hadd2(uint32_t a, uint32_t b) { uint32_t r; asm("add.rn.bf16x2 %0, %1, %2;" : "=r"(r) : "r"(a), "r"(b)); return r; }
__device__ __forceinline__ unsigned ld_acquire(const unsigned* p) { unsigned v; asm volatile("ld.acquire.gpu.global.u32 %0, [%1];" : "=r"(v) : "l"(p) : "memory"); return v; }
__device__ __forceinline__ void ld_relaxed2(const unsigned long long* p, unsigned long long& a, unsigned long long& b) {
  asm volatile("ld.relaxed.gpu.global.v2.b64 {%0,%1}, [%2];" : "=l"(a), "=l"(b) : "l"(p) : "memory");
}
__device__ __forceinline__ void st_relaxed2(unsigned long long* p, unsigned long long a, unsigned long long b) {
  asm volatile("st.relaxed.gpu.global.v2.b64 [%0], {%1,%2};" ::"l"(p), "l"(a), "l"(b) : "memory");
}
__device__ __forceinline__ unsigned long long ld_relaxed(const unsigned long long* p) { unsigned long long a; asm volatile("ld.relaxed.gpu.global.b64 %0, [%1];" : "=l"(a) : "l"(p) : "memory"); return a; }
__device__ __forceinline__ void st_relaxed(unsigned long long* p, unsigned long long a) { asm volatile("st.relaxed.gpu.global.b64 [%0], %1;" ::"l"(p), "l"(a) : "memory"); }
__device__ __forceinline__ void wait_flag(const unsigned* p, unsigned tag, unsigned ns) {
  uint32_t n = 0;
  while (ld_acquire(p) != tag) { if (ns) __nanosleep(ns); if (++n > (1u << 20)) spin_fail(); }
}
__device__ __forceinline__ void red_add_gpu(unsigned* p, unsigned v) { asm volatile("red.relaxed.gpu.global.add.u32 [%0], %1;" ::"l"(p), "r"(v) : "memory"); }

struct cpx { float r, i; };
__device__ __forceinline__ cpx cmul(cpx a, cpx b) { cpx c; c.r = fmaf(a.r, b.r, -a.i * b.i); c.i = fmaf(a.r, b.i, a.i * b.r); return c; }
__device__ __forceinline__ cpx cfma(cpx a, cpx b, cpx c) { cpx d; d.r = fmaf(a.r, b.r, fmaf(-a.i, b.i, c.r)); d.i = fmaf(a.r, b.i, fmaf(a.i, b.r, c.i)); return d; }

constexpr int U_HI = 2240, U_CH = 4496;
constexpr int CU_OFF = 0;
constexpr int CLUT_OFF = CU_OFF + 16 * U_CH;
constexpr int NTAB = 1024;
constexpr int T_P = 0, T_P2 = 560, T_P3 = 816, T_P64 = 976;
constexpr int CW_OFF = CLUT_OFF;
constexpr int Y5_LO = 0, Y5_HI = 1552, Y3_LO = 3104, Y3_HI = 4656, Y9_LO = 6208, Y9_HI = 7232, Y7_LO = 8256, Y7_HI = 9280;
constexpr int W_SIG_BYTES = 10304;
constexpr int KST_PITCH = 144;
constexpr int KST_BYTES = 56 * KST_PITCH;
constexpr int W_TAB = W_SIG_BYTES;
constexpr int W_KD0 = 2 * KST_BYTES;
constexpr int W_KD1 = W_KD0 + 1552;
constexpr int W_PART = KST_BYTES;
constexpr int W_BYTES = W_KD1 + 1552;
constexpr int NCW = 8;
constexpr int CBAR_OFF = CW_OFF + NCW * W_BYTES;
constexpr int CONV_SMEM = CBAR_OFF + 384;

constexpr int pos_of(int l) {
  if (l < 256) return l;
  int s = l < 512 ? 1 : l < 1024 ? 2 : 3;
  int q = l >> s, rem = l & ((1 << s) - 1), half = 1 << (s - 1);
  if (rem > half || (rem == half && (q & 1))) q++;
  return q << s;
}
constexpr int kd_index(int pos) {
  return pos < 256 ? pos : pos < 512 ? 256 + (pos - 256) / 2 : pos < 1024 ? 384 + (pos - 512) / 4 : 512 + (pos - 1024) / 8;
}
__device__ __forceinline__ int kd_slot(int i, int g, int q) {
  const int mt = i / 12, nt = (i / 4) % 3, e = i & 1, j = mt * 16 + g + ((i & 3) >> 1) * 8, c = 2 * q + e;
  if (nt == 0) return 8 * j + c;
  if (nt == 1) return c < 4 ? 256 + c + 4 * j : 384 + 64 * ((c - 4) >> 1) + (c & 1) + 2 * j;
  return c < 4 ? 512 + 32 * c + j : c == 4 ? 640 + j : 672 + j;
}
constexpr int KD_ZERO = 768;
constexpr int tab_elem(int w, int hi) {
  if (w < T_P2) { int l = w - 16 - hi; return (l >= 0 && l <= 514) ? kd_index(pos_of(l)) : KD_ZERO; }
  if (w < T_P3) {
    int psi = (w - T_P2) >> 6, mu = ((w - T_P2) & 63) + 16 - hi;
    if (mu < 32 || mu > 63) return KD_ZERO;
    if (psi == 0) return kd_index(16 * mu + 16);
    return kd_index(16 * mu + 4 * psi);
  }
  if (w < T_P64) {
    int e = (w - T_P3) / 80, mu = (w - T_P3) % 80 + 48 - hi;
    if (mu < 64 || mu > 127) return KD_ZERO;
    return e ? kd_index(16 * mu + 8) : kd_index(16 * mu + 16);
  }
  int l = (w - T_P64) - 16 - hi;
  return (l == 3 || l == 4) ? kd_index(1024) : KD_ZERO;
}
struct alignas(16) Lut {
  uint32_t v[NTAB];
  constexpr Lut() : v() { for (int w = 0; w < NTAB; w++) v[w] = (uint32_t)(tab_elem(w, 0) * 2) | ((uint32_t)(tab_elem(w, 1) * 2) << 16); }
};
__device__ constexpr Lut g_lut{};

__device__ __forceinline__ cpx cexp_fast(float a2, float bt, float pos) {
  float mag;
  asm("ex2.approx.ftz.f32 %0, %1;" : "=f"(mag) : "f"(a2 * pos));
  float th = bt * pos; th -= rintf(th);
  th *= 6.283185307179586f;
  return cpx{mag * __cosf(th), mag * __sinf(th)};
}
__device__ __forceinline__ float bf_sel(uint2 v, int ps) { const uint32_t w = (ps & 2) ? v.y : v.x; return (ps & 1) ? bfhi(w) : bflo(w); }

struct KParams { uint2 a, b, c, d; float ldt; };
__device__ __forceinline__ KParams load_kparams(const Params& P, int ch, int lane) {
  KParams k; const int idx = ch * 32 + lane;
  k.a = __ldg(reinterpret_cast<const uint2*>(P.logA) + idx); k.b = __ldg(reinterpret_cast<const uint2*>(P.Aim) + idx);
  k.c = __ldg(reinterpret_cast<const uint2*>(P.Cre) + idx);  k.d = __ldg(reinterpret_cast<const uint2*>(P.Cim) + idx);
  k.ldt = bf2f(P.logdtA[ch]);
  return k;
}
__device__ __forceinline__ void kgen_pass(const KParams& kp, float dt, int ps, uint32_t st, float (&kacc)[2][3][4]) {
  const int lane = threadIdx.x & 31;
  const float za = -bfround(expf(bf_sel(kp.a, ps))) * dt * 1.4426950408889634f;
  const float zb = bf_sel(kp.b, ps) * dt * 0.15915494309189535f;
  const cpx Cc = {2.f * bf_sel(kp.c, ps) * dt, 2.f * bf_sel(kp.d, ps) * dt};
  const cpx w1 = cexp_fast(za, zb, 1.f), E8 = cexp_fast(za, -zb, 8.f), E256 = cexp_fast(za, zb, 256.f);
  const cpx w2 = cmul(w1, w1), w4 = cmul(w2, w2), E16 = cmul(E8, E8), E32 = cmul(E16, E16);
  const uint32_t fa = st + lane * 4, ra = st + 32 * KST_PITCH + lane * 4;
  {
    cpx f0 = {1.f, 0.f}, f1 = E8, f2 = E16, f3 = cmul(E16, E8);
#pragma unroll
    for (int j = 0; j < 32; j += 4) {
      sts32(fa + j * KST_PITCH, pack_bf16(f0.r, f0.i));
      sts32(fa + (j + 1) * KST_PITCH, pack_bf16(f1.r, f1.i));
      sts32(fa + (j + 2) * KST_PITCH, pack_bf16(f2.r, f2.i));
      sts32(fa + (j + 3) * KST_PITCH, pack_bf16(f3.r, f3.i));
      if (j < 28) { f0 = cmul(f0, E32); f1 = cmul(f1, E32); f2 = cmul(f2, E32); f3 = cmul(f3, E32); }
    }
  }
  {
    cpx r = Cc, big = cmul(Cc, E256);
#pragma unroll
    for (int b = 0; b < 8; b++) { sts32(ra + b * KST_PITCH, pack_bf16(r.r, r.i)); if (b < 7) r = cmul(r, w1); }
    r = big;
#pragma unroll
    for (int b = 8; b < 12; b++) { sts32(ra + b * KST_PITCH, pack_bf16(r.r, r.i)); if (b < 11) r = cmul(r, w2); }
    big = cmul(big, E256);
    sts32(ra + 12 * KST_PITCH, pack_bf16(big.r, big.i)); r = cmul(big, w4); sts32(ra + 13 * KST_PITCH, pack_bf16(r.r, r.i));
    big = cmul(big, E256);
    sts32(ra + 14 * KST_PITCH, pack_bf16(big.r, big.i)); r = cmul(big, w4); sts32(ra + 15 * KST_PITCH, pack_bf16(r.r, r.i));
#pragma unroll
    for (int b = 16; b < 21; b++) { big = cmul(big, E256); sts32(ra + b * KST_PITCH, pack_bf16(big.r, big.i)); }
#pragma unroll
    for (int b = 21; b < 24; b++) sts32(ra + b * KST_PITCH, 0u);
  }
  __syncwarp();
#pragma unroll
  for (int ks = 0; ks < 4; ks++) {
    const int m = lane >> 3, rr = lane & 7;
    uint32_t A0[4], A1[4], Bq[4], B2a, B2b;
    ldsm4(A0, st + ((m & 1) * 8 + rr) * KST_PITCH + ks * 32 + (m >> 1) * 16);
    ldsm4(A1, st + (16 + (m & 1) * 8 + rr) * KST_PITCH + ks * 32 + (m >> 1) * 16);
    ldsm4(Bq, st + (32 + (m >> 1) * 8 + rr) * KST_PITCH + ks * 32 + (m & 1) * 16);
    ldsm2(B2a, B2b, st + (48 + rr) * KST_PITCH + ks * 32 + (m & 1) * 16);
    mma16816(kacc[0][0], A0[0], A0[1], A0[2], A0[3], Bq[0], Bq[1]);
    mma16816(kacc[0][1], A0[0], A0[1], A0[2], A0[3], Bq[2], Bq[3]);
    mma16816(kacc[0][2], A0[0], A0[1], A0[2], A0[3], B2a, B2b);
    mma16816(kacc[1][0], A1[0], A1[1], A1[2], A1[3], Bq[0], Bq[1]);
    mma16816(kacc[1][1], A1[0], A1[1], A1[2], A1[3], Bq[2], Bq[3]);
    mma16816(kacc[1][2], A1[0], A1[1], A1[2], A1[3], B2a, B2b);
  }
  __syncwarp();
}

__device__ __forceinline__ void build_signals(uint32_t ub, uint32_t wb, int lane) {
    {
      float pre[65];
      pre[0] = 0.f;
#pragma unroll
      for (int cc = 0; cc < 8; cc++) {
        const int e0 = 48 * lane - 16 + cc * 8;
        const uint4 v = lds128(ub + ((e0 >> 3) & 1) * U_HI + (8 + (e0 >> 4)) * 16);
        const uint32_t ww[4] = {v.x, v.y, v.z, v.w};
#pragma unroll
        for (int k = 0; k < 4; k++) { pre[cc * 8 + 2 * k + 1] = pre[cc * 8 + 2 * k] + bflo(ww[k]); pre[cc * 8 + 2 * k + 2] = pre[cc * 8 + 2 * k + 1] + bfhi(ww[k]); }
      }
#pragma unroll
      for (int cc = 0; cc < 6; cc++) {
        uint32_t o5[4], o3[4];
#pragma unroll
        for (int k = 0; k < 4; k++) {
          const int i0 = cc * 8 + 2 * k + 16;
          o5[k] = pack_bf16(pre[i0 - 5] - pre[i0 - 10], pre[i0 - 4] - pre[i0 - 9]);
          o3[k] = pack_bf16(pre[i0 - 2] - pre[i0 - 5], pre[i0 - 1] - pre[i0 - 4]);
        }
        const int i = 48 * lane + cc * 8;
        const uint32_t off = (1 + (i >> 4)) * 16;
        sts128(wb + (((i >> 3) & 1) ? Y5_HI : Y5_LO) + off, make_uint4(o5[0], o5[1], o5[2], o5[3]));
        sts128(wb + (((i >> 3) & 1) ? Y3_HI : Y3_LO) + off, make_uint4(o3[0], o3[1], o3[2], o3[3]));
      }
      if (lane < 4) sts128(wb + (lane == 0 ? Y5_LO : lane == 1 ? Y5_HI : lane == 2 ? Y3_LO : Y3_HI), make_uint4(0, 0, 0, 0));
    }
    {
      float pre[57];
      pre[0] = 0.f;
#pragma unroll
      for (int cc = 0; cc < 7; cc++) {
        const int e0 = 32 * lane - 24 + cc * 8;
        const uint4 v = lds128(ub + ((e0 >> 3) & 1) * U_HI + (8 + (e0 >> 4)) * 16);
        const uint32_t ww[4] = {v.x, v.y, v.z, v.w};
#pragma unroll
        for (int k = 0; k < 4; k++) { pre[cc * 8 + 2 * k + 1] = pre[cc * 8 + 2 * k] + bflo(ww[k]); pre[cc * 8 + 2 * k + 2] = pre[cc * 8 + 2 * k + 1] + bfhi(ww[k]); }
      }
#pragma unroll
      for (int cc = 0; cc < 4; cc++) {
        uint32_t o9[4], o7[4];
#pragma unroll
        for (int k = 0; k < 4; k++) {
          const int i0 = cc * 8 + 2 * k + 24;
          o9[k] = pack_bf16(pre[i0 - 11] - pre[i0 - 20], pre[i0 - 10] - pre[i0 - 19]);
          o7[k] = pack_bf16(pre[i0 - 4] - pre[i0 - 11], pre[i0 - 3] - pre[i0 - 10]);
        }
        const int i = 32 * lane + cc * 8;
        const uint32_t off = (i >> 4) * 16;
        sts128(wb + (((i >> 3) & 1) ? Y9_HI : Y9_LO) + off, make_uint4(o9[0], o9[1], o9[2], o9[3]));
        sts128(wb + (((i >> 3) & 1) ? Y7_HI : Y7_LO) + off, make_uint4(o7[0], o7[1], o7[2], o7[3]));
      }
    }
}

__device__ __forceinline__ void build_tables(uint32_t kdb, uint32_t tab, const uint32_t* lut, int lane) {
  uint32_t ix[32];
#pragma unroll
  for (int k = 0; k < 32; k++) ix[k] = __ldg(lut + k * 32 + lane);
  uint32_t lo[32], hi[32];
#pragma unroll
  for (int k = 0; k < 32; k++) { lo[k] = lds16(kdb + (ix[k] & 0xFFFF)); hi[k] = lds16(kdb + (ix[k] >> 16)); }
#pragma unroll
  for (int k = 0; k < 32; k++) sts32(tab + (k * 32 + lane) * 4, lo[k] | (hi[k] << 16));
  __syncwarp();
}
__device__ __noinline__ void conv_channel(uint32_t ub, uint32_t wb, uint32_t tab, uint32_t sig_bar, __nv_bfloat16* ydst, unsigned* ycnt) {
  const int lane = threadIdx.x & 31, g = lane >> 2, q = lane & 3;
  {
    float acc[16][4];
#pragma unroll
    for (int G = 0; G < 16; G++) { acc[G][0] = acc[G][1] = acc[G][2] = acc[G][3] = 0.f; }
    const uint32_t tb = tab + (g - 2 * q) * 4;
    const int lm = lane >> 3, lr = lane & 7;
#pragma unroll 1
    for (int eps = 0; eps < 8; eps++) {
      uint32_t Vm[4], V0[4], Vp[4];
#pragma unroll
      for (int ga = 0; ga < 4; ga++) {
        const uint32_t a = tb + (T_P + 16 + 8 * (16 * ga + 2 * eps)) * 4;
        Vm[ga] = lds32(a - 32); V0[ga] = lds32(a); Vp[ga] = lds32(a + 32);
      }
      const uint32_t ba = ub + (lm & 1) * U_HI + (8 + (lm >> 1) * 32 - eps + lr) * 16;
#pragma unroll
      for (int G0 = 0; G0 < 4; G0++) {
        uint32_t Ba[4], Bb[4];
        ldsm4(Ba, ba + G0 * 128);
        ldsm4(Bb, ba + (G0 + 8) * 128);
#pragma unroll
        for (int ga = 0; ga < 4; ga++) {
          mma16816(acc[G0 + ga], V0[ga], Vp[ga], Vm[ga], V0[ga], Ba[0], Ba[1]);
          if (G0 + 4 + ga < 16) mma16816(acc[G0 + 4 + ga], V0[ga], Vp[ga], Vm[ga], V0[ga], Ba[2], Ba[3]);
          if (G0 + 8 + ga < 16) mma16816(acc[G0 + 8 + ga], V0[ga], Vp[ga], Vm[ga], V0[ga], Bb[0], Bb[1]);
          if (G0 + 12 + ga < 16) mma16816(acc[G0 + 12 + ga], V0[ga], Vp[ga], Vm[ga], V0[ga], Bb[2], Bb[3]);
        }
      }
    }
#pragma unroll 1
    for (int eps = 0; eps < 2; eps++) {
      const uint32_t a = tb + (T_P + 16 + 8 * (64 + 2 * eps)) * 4;
      const uint32_t Vm = lds32(a - 32), V0 = lds32(a), Vp = lds32(a + 32);
      const uint32_t a2 = tb + (T_P64 + 16 + 16 * eps) * 4;
      const uint32_t Wm = lds32(a2 - 32), W0 = lds32(a2), Wp = lds32(a2 + 32);
      const uint32_t ba = ub + (lm & 1) * U_HI + (8 + (lm >> 1) * 8 - eps + lr) * 16;
#pragma unroll
      for (int GG = 0; GG < 12; GG += 2) {
        uint32_t B[4];
        ldsm4(B, ba + GG * 128);
#pragma unroll
        for (int k = 0; k < 2; k++) {
          mma16816(acc[GG + k + 4], V0, Vp, Vm, V0, B[2 * k], B[2 * k + 1]);
          if (GG + k + 8 < 16) mma16816(acc[GG + k + 8], W0, Wp, Wm, W0, B[2 * k], B[2 * k + 1]);
        }
      }
    }
    if (sig_bar) mbar_wait(sig_bar, 0);
#pragma unroll 1
    for (int psi = 0; psi < 4; psi++) {
      uint32_t Vt[7];
#pragma unroll
      for (int k = 0; k < 7; k++) Vt[k] = lds32(tb + (T_P2 + psi * 64 + 8 * (k + 3) - 16) * 4);
      const uint32_t lo = wb + ((psi & 1) ? Y3_LO : Y5_LO), hi = wb + ((psi & 1) ? Y3_HI : Y5_HI);
      const bool sh = (psi == 0 || psi == 3);
      const uint32_t aa = sh ? ((lm & 1) ? lo + 16 : hi) : ((lm & 1) ? hi + 16 : lo + 16);
      const uint32_t ab = aa + ((lm >> 1) * 8 + lr) * 16;
#pragma unroll
      for (int z = 0; z <= 10; z += 2) {
        uint32_t A[4];
        ldsm4t(A, ab + z * 128);
#pragma unroll
        for (int la = 4; la <= 9; la++)
          if (z + la < 16) mma16816(acc[z + la], A[0], A[1], A[2], A[3], Vt[la - 3], Vt[la - 4]);
      }
    }
#pragma unroll 1
    for (int e = 0; e < 2; e++) {
      uint32_t Vt[9];
#pragma unroll
      for (int k = 0; k < 9; k++) Vt[k] = lds32(tb + (T_P3 + e * 80 + 8 * (k + 7) - 48) * 4);
      const uint32_t lo = wb + (e ? Y7_LO : Y9_LO), hi = wb + (e ? Y7_HI : Y9_HI);
      const uint32_t ab = ((lm & 1) ? hi : lo) + ((lm >> 1) * 8 + lr) * 16;
#pragma unroll
      for (int z = 0; z <= 6; z += 2) {
        uint32_t A[4];
        ldsm4t(A, ab + z * 128);
#pragma unroll
        for (int la = 8; la <= 15; la++)
          if (z + la < 16) mma16816(acc[z + la], A[0], A[1], A[2], A[3], Vt[la - 7], Vt[la - 8]);
      }
    }
    __syncwarp();
    const uint32_t ob = tab + (8 * (g >> 1) + 2 * q + (g & 1)) * 2;
#pragma unroll
    for (int G = 0; G < 16; G++)
#pragma unroll
      for (int i = 0; i < 4; i++) sts16(ob + (128 * G + 64 * (i & 1) + 32 * (i >> 1)) * 2, pack_bf16(acc[G][i], 0.f) & 0xFFFFu);
    fence_async_smem();
    __syncwarp();
    if (lane == 0) {
      bulk_s2g(ydst, tab, 4096);
      bulk_commit();
      bulk_wait0();
      red_add_gpu(ycnt, 1u);
    }
    __syncwarp();
  }
}

constexpr int S1_STAGE = 40960, S1_A = 24576, NS1 = 4;
constexpr int S2_H = 16384, S2_C = 12288, NS2 = 6;
constexpr int WK_OFF = NS2 * S2_H;
constexpr int WK_BYTES = 18896, WK_TAB = 10304, WK_U = 14400;
constexpr int C_OFF = WK_OFF + 57344;
constexpr int EX_OFF = WK_OFF;
constexpr int EY_OFF = WK_OFF + 32768;
constexpr int BAR_OFF = C_OFF + NS2 * S2_C;
constexpr int B_FULL1 = 0, B_EMPTY1 = 4, B_G1DONE = 8, B_HR = 9, B_FULL2 = 12, B_EMPTY2 = 18, B_WDONE = 24, B_EPI = 25, B_LB = 26, B_PUB = 27, B_WFULL = 29;
constexpr int DSK_OFF = BAR_OFF + 256;
constexpr int S5_SMEM = DSK_OFF + 384;
__device__ __forceinline__ constexpr int cslot(int i) { return (i + 1) % 6; }

__device__ __forceinline__ unsigned load_tag(const Scratch* ws) {
  unsigned e;
  asm volatile("ld.relaxed.gpu.global.u32 %0, [%1];" : "=r"(e) : "l"(&ws->epoch[blockIdx.x * 32]) : "memory");
  return e + 1u;
}

__device__ __forceinline__ void s5_role(const Params& P, const CUtensorMap* tmX, const CUtensorMap* tmB, const CUtensorMap* tmC, const CUtensorMap* tmY,
                                        uint32_t sb, long long t_start) {
  const int tid = threadIdx.x, warp = __shfl_sync(0xffffffffu, tid >> 5, 0), lane = tid & 31;
  const int c = blockIdx.x / 6, sg = blockIdx.x % 6;
  const uint32_t rank = sg & 1;
  const uint32_t bars = sb + BAR_OFF;
  auto BAR = [&](int i) { return bars + 8u * (uint32_t)i; };

  if (tid == 384) {
    asm volatile("prefetch.tensormap [%0];" ::"l"(tmB) : "memory");
    asm volatile("prefetch.tensormap [%0];" ::"l"(tmX) : "memory");
#pragma unroll
    for (int i = 0; i < NS1; i++) { mbar_init(BAR(B_FULL1 + i), 1); mbar_init(BAR(B_EMPTY1 + i), 24); }
    mbar_init(BAR(B_G1DONE), 24);
#pragma unroll
    for (int i = 0; i < 3; i++) mbar_init(BAR(B_HR + i), 4);
#pragma unroll
    for (int i = 0; i < NS2; i++) { mbar_init(BAR(B_FULL2 + i), 1); mbar_init(BAR(B_EMPTY2 + i), 16); }
    mbar_init(BAR(B_WDONE), 3); mbar_init(BAR(B_EPI), 2); mbar_init(BAR(B_LB), 12); mbar_init(BAR(B_PUB), 1); mbar_init(BAR(B_PUB + 1), 1);
#pragma unroll
    for (int i = 0; i < 3; i++) mbar_init(BAR(B_WFULL + i), 1);
    asm volatile("fence.mbarrier_init.release.cluster;" ::: "memory");
  }
  if (tid == 384) STAMP(38);
  asm volatile("barrier.cluster.arrive.release.aligned;" ::: "memory");
  if (tid == 384) STAMP(39);
  if (tid == 0) STAMP(40);

  if (warp >= 12) {
    if (warp == 12) {
      auto kb_of = [&](int i) {
        if (i < 3) return sg * 3 + i;
        const int j = (i - 3) / 5, r = (i - 3) % 5;
        int s2 = r == 0 ? (sg ^ 1) : ((sg >> 1) * 2 + 1 + r);
        if (s2 >= 6) s2 -= 6;
        return s2 * 3 + j;
      };
      if (lane == 0) {
        mbar_expect_tx(BAR(B_FULL1), S1_STAGE);
        tma5d(sb + S1_A, tmX, BAR(B_FULL1), 0, 0, 0, 0, c);
        tma5d(sb + S1_A + 8192, tmX, BAR(B_FULL1), 0, 0, 0, 8, c);
        tma4d(sb, tmB, BAR(B_FULL1), 0, 0, 0, sg * 12);
      }
      if (lane == 0) STAMP(41);
      asm volatile("barrier.cluster.wait.acquire.aligned;" ::: "memory");
      if (lane == 0) {
        STAMP(0);
        for (int kb = 0; kb < 9; kb++) {
          const int s = kb & 3;
          if (kb >= NS1) mbar_wait(BAR(B_EMPTY1 + s), 0 ^ (kb >= 8));
          if (kb > 0) mbar_expect_tx(BAR(B_FULL1 + s), S1_STAGE);
          if (kb > 0) tma5d_mc(sb + s * S1_STAGE + S1_A + rank * 8192, tmX, BAR(B_FULL1 + s), kb * 64, 0, 0, (int)rank * 8, c, (uint16_t)3);
          if (kb > 0) tma4d(sb + s * S1_STAGE, tmB, BAR(B_FULL1 + s), kb * 64, 0, 0, sg * 12);
          if (kb == 0) { asm volatile("prefetch.tensormap [%0];" ::"l"(tmC) : "memory"); asm volatile("prefetch.tensormap [%0];" ::"l"(tmY) : "memory"); }
          if (kb >= 4) {
            const int i = kb - 4;
            mbar_expect_tx(BAR(B_FULL2 + i), i < 3 ? S2_C : S2_C + S2_H);
            tma3d(sb + C_OFF + cslot(i) * S2_C, tmC, BAR(B_FULL2 + i), kb_of(i) * 32, sg * 96, 0);
          }
        }
        mbar_wait(BAR(B_LB), 0);
        mbar_wait(BAR(B_G1DONE), 0);
        mbar_expect_tx(BAR(B_FULL2 + 5), S2_C + S2_H);
        tma3d(sb + C_OFF + cslot(5) * S2_C, tmC, BAR(B_FULL2 + 5), kb_of(5) * 32, sg * 96, 0);
      }
      const unsigned tag = load_tag(P.ws);
      __syncwarp();
#pragma unroll 1
      for (int j = 0; j < 3; j++) {
        if (lane < 5) wait_flag(&P.ws->hflag[c * 18 + kb_of(3 + 5 * j + lane)], tag, 0);
        __syncwarp();
        if (lane == 0) {
          if (j == 0) STAMP(15);
          for (int r = 0; r < 5; r++) {
            const int i = 3 + 5 * j + r, s = i % 6, kb = kb_of(i);
            if (i >= 6) {
              mbar_wait(BAR(B_EMPTY2 + s), i >= 12);
              mbar_expect_tx(BAR(B_FULL2 + s), S2_C + S2_H);
              tma3d(sb + C_OFF + cslot(i) * S2_C, tmC, BAR(B_FULL2 + s), kb * 32, sg * 96, 0);
            }
            const unsigned char* src = P.ws->H + (size_t)(c * 18 + kb) * 16384;
            if (r == 0) bulk_g2s(sb + s * S2_H, src, S2_H, BAR(B_FULL2 + s));
            else bulk_g2s_mc(sb + s * S2_H + rank * 8192, src + rank * 8192, 8192, BAR(B_FULL2 + s), (uint16_t)3);
          }
        }
        __syncwarp();
      }
      if (lane == 0) {
        mbar_wait(BAR(B_WDONE), 0);
        mbar_expect_tx(BAR(B_EPI), 32768);
        for (int m = 0; m < 2; m++)
          for (int cb = 0; cb < 2; cb++)
            tma5d(sb + EX_OFF + (m * 2 + cb) * 8192, tmX, BAR(B_EPI), sg * 96 + cb * 64, 0, 0, m * 8, c);
      }
    } else {
      asm volatile("barrier.cluster.wait.acquire.aligned;" ::: "memory");
      const int j = warp - 13;
      const unsigned tag = load_tag(P.ws);
      if (j == 0) {
        for (int i = lane; i < 48; i += 32) {
          sts32(sb + DSK_OFF + i * 4, reinterpret_cast<const uint32_t*>(P.DskA)[sg * 48 + i]);
          sts32(sb + DSK_OFF + 192 + i * 4, reinterpret_cast<const uint32_t*>(P.DskB)[sg * 48 + i]);
        }
      }
      __syncwarp();
      asm volatile("bar.arrive 4, 352;" ::: "memory");
      {
        const int r0 = sg * 21 + min(sg, 2), nr = sg < 2 ? 22 : 21;
        uint32_t gw[9];
#pragma unroll
        for (int i = 0; i < 9; i++) gw[i] = reinterpret_cast<const uint32_t*>(P.gw)[i * 32 + lane];
#pragma unroll 1
        for (int rb = j; rb < nr; rb += 12) {
          uint32_t xv[4][9];
#pragma unroll
          for (int k = 0; k < 4; k++) {
            const int r = min(rb + 3 * k, nr - 1);
            const uint32_t* xr = reinterpret_cast<const uint32_t*>(P.u + (size_t)(c * 128 + r0 + r) * D_);
#pragma unroll
            for (int i = 0; i < 9; i++) xv[k][i] = __ldg(xr + i * 32 + lane);
          }
#pragma unroll
          for (int k = 0; k < 4; k++) {
            float s = 0.f;
#pragma unroll
            for (int i = 0; i < 9; i++) { uint32_t pr = hmul2(xv[k][i], gw[i]); s += bflo(pr) + bfhi(pr); }
#pragma unroll
            for (int o = 16; o > 0; o >>= 1) s += __shfl_xor_sync(0xffffffffu, s, o);
            if (lane == 0 && rb + 3 * k < nr) {
              float z = bfround(s);
              float g = bfround(1.f / (1.f + __expf(-z)));
              st_relaxed(&P.ws->gate[c * 128 + r0 + rb + 3 * k], ((unsigned long long)tag << 32) | __float_as_uint(g));
            }
          }
        }
      }
      {
        const int n = blockIdx.x * 3 + j, ch = (n >> 3) * 16 + (n & 7);
        const uint32_t wk = sb + WK_OFF + j * WK_BYTES;
        if (lane == 0) {
          wait_flag(&P.ws->kflag[ch], tag, 0);
          mbar_wait(BAR(B_G1DONE), 0);
          mbar_expect_tx(BAR(B_WFULL + j), 4496 + 1552);
          bulk_g2s(wk + WK_U, P.ws->uT + (size_t)n * 4496, 4496, BAR(B_WFULL + j));
          bulk_g2s(wk, P.ws->kd + (size_t)ch * 776, 1552, BAR(B_WFULL + j));
        }
        __syncwarp();
        mbar_wait(BAR(B_WFULL + j), 0);
        if (tid == 416) STAMP(44);
        build_tables(wk, wk + WK_TAB, P.lut, lane);
        build_signals(wk + WK_U, wk, lane);
        __syncwarp();
        conv_channel(wk + WK_U, wk, wk + WK_TAB, 0, P.ws->y + (size_t)ch * L_, &P.ws->ycnt[(ch / 96) * 32]);
        if (lane == 0) mbar_arrive(BAR(B_WDONE));
        if (tid == 416) STAMP(45);
      }
      if (j == 0 && lane == 0) {
        wait_flag(&P.ws->ycnt[sg * 32], tag * 96u, 0);
        mbar_wait(BAR(B_WDONE), 0);
        mbar_expect_tx(BAR(B_EPI), 24576);
        for (int m = 0; m < 2; m++) tma2d(sb + EY_OFF + m * 12288, tmY, BAR(B_EPI), c * 128 + m * 64, sg * 96);
      }
    }
  } else {
    const int wg = warp >> 2, w = warp & 3, g = lane >> 2, q = lane & 3;
    const int p = sg * 96 + wg * 32 + w * 8 + g;
    const float ldtB = bf2f(P.logdtB[p]), lr = bf2f(P.Lre[p]), li = bf2f(P.Lim[p]);
    const unsigned tag = load_tag(P.ws);
    cpx Lb; float c1, c2, c3, c4;
    {
      float dt = bfround(expf(ldtB));
      float zr = dt * lr, zi = dt * li;
      float e = expf(zr), sn, cs;
      sincospif(zi * 0.3183098861837907f, &sn, &cs);
      Lb.r = e * cs; Lb.i = e * sn;
      float nr_ = Lb.r - 1.f, ni_ = Lb.i, den = 2.f / (lr * lr + li * li);
      float Fr = (nr_ * lr + ni_ * li) * den, Fi = (ni_ * lr - nr_ * li) * den;
      if (!P.swapB) { c1 = Fr; c2 = -Fi; c3 = -Fi; c4 = -Fr; }
      else { c1 = -Fi; c2 = Fr; c3 = -Fr; c4 = -Fi; Lb.i = -Lb.i; }
      if (P.swapC) { float t1 = c1, t2 = c2; c1 = c3; c2 = c4; c3 = t1; c4 = t2; }
    }

    asm volatile("barrier.cluster.wait.acquire.aligned;" ::: "memory");
    float d[64];
    for (int kb = 0; kb < 9; kb++) {
      const int s = kb & 3;
      mbar_wait(BAR(B_FULL1 + s), (kb >> 2) & 1);
      if (tid == 0) STAMP(1 + kb);
      const uint64_t da = desc_sw128(sb + s * S1_STAGE + wg * 8192), db = desc_sw128(sb + s * S1_STAGE + S1_A);
      wg_fence();
#pragma unroll
      for (int ks = 0; ks < 4; ks++) wgmma_ss_n128(d, da + 2 * ks, db + 2 * ks, (kb | ks) != 0);
      wg_commit();
      if (kb >= 1 && kb <= 5) {
        wg_wait<1>();
        if (lane == 0) { mbar_arrive_cluster(mapa(BAR(B_EMPTY1 + ((kb - 1) & 3)), 0)); mbar_arrive_cluster(mapa(BAR(B_EMPTY1 + ((kb - 1) & 3)), 1)); }
      }
    }
    wg_wait<0>();
    const cpx L2 = cmul(Lb, Lb), L4 = cmul(L2, L2), L8 = cmul(L4, L4), L16 = cmul(L8, L8), L32 = cmul(L16, L16), L64 = cmul(L32, L32), L128 = cmul(L64, L64);
    if (tid == 0) STAMP(10);
    if (lane == 0) { mbar_arrive_cluster(mapa(BAR(B_G1DONE), 0)); mbar_arrive_cluster(mapa(BAR(B_G1DONE), 1)); }

    cpx e;
    {
      cpx ea = {d[0], d[2]}, eb = {d[32], d[34]};
      ea = cfma(ea, Lb, cpx{d[1], d[3]}); eb = cfma(eb, Lb, cpx{d[33], d[35]});
#pragma unroll
      for (int jj = 1; jj < 8; jj++) {
        ea = cfma(ea, Lb, cpx{d[4 * jj], d[4 * jj + 2]});          eb = cfma(eb, Lb, cpx{d[32 + 4 * jj], d[32 + 4 * jj + 2]});
        ea = cfma(ea, Lb, cpx{d[4 * jj + 1], d[4 * jj + 3]});      eb = cfma(eb, Lb, cpx{d[32 + 4 * jj + 1], d[32 + 4 * jj + 3]});
      }
      e = cfma(ea, L16, eb);
    }
    {
      cpx t; t.r = __shfl_up_sync(0xffffffffu, e.r, 1, 4); t.i = __shfl_up_sync(0xffffffffu, e.i, 1, 4);
      if (q >= 1) e = cfma(t, L32, e);
      t.r = __shfl_up_sync(0xffffffffu, e.r, 2, 4); t.i = __shfl_up_sync(0xffffffffu, e.i, 2, 4);
      if (q >= 2) e = cfma(t, L64, e);
    }
    if (q == 3) st_relaxed2(&P.ws->agg[(size_t)(c * 576 + p) * 2], ((unsigned long long)tag << 32) | __float_as_uint(e.r), ((unsigned long long)tag << 32) | __float_as_uint(e.i));
    cpx ex; ex.r = __shfl_up_sync(0xffffffffu, e.r, 1, 4); ex.i = __shfl_up_sync(0xffffffffu, e.i, 1, 4);
    if (q == 0) { ex.r = 0.f; ex.i = 0.f; }
    if (tid == 0) STAMP(11);
    cpx carry = {0.f, 0.f};
    {
      const cpx L256 = cmul(L128, L128), L512 = cmul(L256, L256);
      const unsigned long long* ap = &P.ws->agg[(size_t)(q * 576 + p) * 2];
      unsigned long long a[4], b[4];
      uint32_t n = 0;
      while (true) {
        bool ok = true;
#pragma unroll
        for (int k = 0; k < 4; k++)
          if (q + 4 * k < c) ld_relaxed2(ap + (size_t)k * 4 * 576 * 2, a[k], b[k]);
#pragma unroll
        for (int k = 0; k < 4; k++)
          if (q + 4 * k < c) ok = ok && (unsigned)(a[k] >> 32) == tag && (unsigned)(b[k] >> 32) == tag;
        if (ok) break;
        if (++n > (1u << 20)) spin_fail();
      }
#pragma unroll
      for (int k = 0; k < 4; k++)
        if (q + 4 * k < c) carry = cfma(carry, L512, cpx{__uint_as_float((unsigned)a[k]), __uint_as_float((unsigned)b[k])});
      const int ee = (c - 1 - q) & 3;
      if (ee & 1) carry = cmul(carry, L128);
      if (ee & 2) carry = cmul(carry, L256);
      carry.r += __shfl_xor_sync(0xffffffffu, carry.r, 1); carry.i += __shfl_xor_sync(0xffffffffu, carry.i, 1);
      carry.r += __shfl_xor_sync(0xffffffffu, carry.r, 2); carry.i += __shfl_xor_sync(0xffffffffu, carry.i, 2);
      if (q & 1) carry = cmul(carry, L32);
      if (q & 2) carry = cmul(carry, L64);
    }
    cpx h = {ex.r + carry.r, ex.i + carry.i};
    if (lane == 0) mbar_arrive(BAR(B_LB));
    if (tid == 0) STAMP(12);
    mbar_wait(BAR(B_G1DONE), 0);
    {
      const int m = lane >> 3, cc = lane & 7;
      const uint32_t abase = sb + wg * S2_H + (m & 1) * 8192 + ((m >> 1) * 8 + cc) * 64 + ((w ^ (cc >> 1)) << 4);
#pragma unroll
      for (int jj = 0; jj < 16; jj += 2) {
        uint32_t r[4];
#pragma unroll
        for (int k = 0; k < 2; k++) {
          h = cfma(h, Lb, cpx{d[4 * (jj + k)], d[4 * (jj + k) + 2]});
          const float a0 = fmaf(c1, h.r, c2 * h.i), b0 = fmaf(c3, h.r, c4 * h.i);
          h = cfma(h, Lb, cpx{d[4 * (jj + k) + 1], d[4 * (jj + k) + 3]});
          const float a1 = fmaf(c1, h.r, c2 * h.i), b1 = fmaf(c3, h.r, c4 * h.i);
          r[2 * k] = pack_bf16(a0, a1); r[2 * k + 1] = pack_bf16(b0, b1);
        }
        stsm4t(abase + jj * 512, r[0], r[1], r[2], r[3]);
      }
    }
    fence_async_smem();
    __syncwarp();
    if (lane == 0) mbar_arrive(BAR(B_HR + wg));
    if (tid == 0) STAMP(13);

    if (warp == 11 && lane == 0) {
      for (int j = 0; j < 3; j++) {
        mbar_wait(BAR(B_HR + j), 0);
        bulk_s2g(P.ws->H + (size_t)(c * 18 + sg * 3 + j) * 16384, sb + j * S2_H, S2_H);
        bulk_commit();
        bulk_wait0();
        st_relaxed_u32(&P.ws->hflag[c * 18 + sg * 3 + j], tag);
        if (j == 0) STAMP(14);
      }
    }
    if (wg < 2) {
      float y[48];
      const uint64_t da0 = desc_sw64(sb + wg * 4096), db0 = desc_sw64(sb + C_OFF);
      const uint32_t e2l = mapa(BAR(B_EMPTY2), 0), e2r = mapa(BAR(B_EMPTY2), 1);
#pragma unroll
      for (int ip = 0; ip < 9; ip++) {
#pragma unroll
        for (int k = 0; k < 2; k++) {
          const int i = 2 * ip + k, s = i % 6;
          if (i < 3) mbar_wait(BAR(B_HR + i), 0);
          mbar_wait(BAR(B_FULL2 + s), (i / 6) & 1);
          if (tid == 0) STAMP(16 + i);
          const uint64_t da = da0 + (uint64_t)(s * (S2_H >> 4)), db = db0 + (uint64_t)(cslot(i) * (S2_C >> 4));
          wg_fence();
          wgmma_ss_n96(y, da, db, i != 0);
          wgmma_ss_n96(y, da + 2, db + 2, 1);
          wgmma_ss_n96(y, da + 512, db + 384, 1);
          wgmma_ss_n96(y, da + 514, db + 386, 1);
        }
        wg_commit();
        if (ip >= 1 && ip <= 6) {
          wg_wait<1>();
          if (lane == 0) {
            const int s0 = (2 * ip - 2) % 6;
            mbar_arrive_cluster(e2l + s0 * 8); mbar_arrive_cluster(e2r + s0 * 8);
            mbar_arrive_cluster(e2l + s0 * 8 + 8); mbar_arrive_cluster(e2r + s0 * 8 + 8);
          }
        }
      }
      wg_wait<0>();
      named_bar(4, 352);
      float gv[2];
      int trow[2];
#pragma unroll
      for (int hh = 0; hh < 2; hh++) {
        trow[hh] = c * 128 + 32 * (g >> 1) + 2 * (8 * wg + 2 * w + hh) + (g & 1);
        unsigned long long v; uint32_t n = 0;
        do { v = ld_relaxed(&P.ws->gate[trow[hh]]); if (++n > (1u << 22)) spin_fail(); } while ((unsigned)(v >> 32) != tag);
        gv[hh] = __uint_as_float((unsigned)v);
      }
      if (tid == 0) STAMP(34);
      mbar_wait(BAR(B_EPI), 0);
      if (tid == 0) STAMP(36);
      uint32_t g2[2]; float omg[2];
#pragma unroll
      for (int hh = 0; hh < 2; hh++) { g2[hh] = pack_bf16(gv[hh], gv[hh]); omg[hh] = bfround(1.f - gv[hh]); }
      float* o0 = P.out + (size_t)trow[0] * D_ + sg * 96 + q * 2;
      float* o1 = P.out + (size_t)trow[1] * D_ + sg * 96 + q * 2;
#pragma unroll
      for (int jp = 0; jp < 6; jp++) {
        uint32_t yc[4];
        {
          const int m = lane >> 3, rr = lane & 7;
          const int dl = (2 * jp + (m >> 1)) * 8 + rr;
          ldsm4t(yc, sb + EY_OFF + wg * 12288 + dl * 128 + (((2 * w + (m & 1)) ^ rr) << 4));
        }
#pragma unroll
        for (int k = 0; k < 2; k++) {
          const int jn = 2 * jp + k;
          const uint32_t dA = lds32(sb + DSK_OFF + (jn * 4 + q) * 4), dB = lds32(sb + DSK_OFF + 192 + (jn * 4 + q) * 4);
#pragma unroll
          for (int hh = 0; hh < 2; hh++) {
            const int rl = 16 * w + 8 * hh + g;
            const uint32_t xv = lds32(sb + EX_OFF + (wg * 2 + (jn >> 3)) * 8192 + rl * 128 + (((jn & 7) ^ g) << 4) + q * 4);
            const uint32_t a2 = hadd2(yc[2 * k + hh], hmul2(xv, dA));
            const uint32_t ga = hmul2(g2[hh], a2);
            const uint32_t ub = hmul2(xv, dB);
            float2 o;
            o.x = fmaf(omg[hh], y[4 * jn + 2 * hh] + bflo(ub), bflo(ga));
            o.y = fmaf(omg[hh], y[4 * jn + 2 * hh + 1] + bfhi(ub), bfhi(ga));
            *reinterpret_cast<float2*>((hh ? o1 : o0) + jn * 8) = o;
          }
        }
      }
    }
  }
  if (tid == 0) STAMP(37);
  asm volatile("barrier.cluster.arrive.relaxed.aligned;\nbarrier.cluster.wait.aligned;" ::: "memory");
}

__device__ __forceinline__ void conv_role(const Params& P, const CUtensorMap* tmU, uint32_t sb, long long t_start) {
  const int tid = threadIdx.x, warp = __shfl_sync(0xffffffffu, tid >> 5, 0), lane = tid & 31;
  const int cb = blockIdx.x - N_S5, ch0 = cb * 16;
  const uint32_t B_ULAND = sb + CBAR_OFF, B_URDY = B_ULAND + 8, B_KPART = B_ULAND + 16, B_KDRDY = B_KPART + 128, B_SFREE = B_KDRDY + 64, B_SFULL = B_SFREE + 64;
  if (tid == 0) {
    asm volatile("prefetch.tensormap [%0];" ::"l"(tmU) : "memory");
    mbar_init(B_ULAND, 1); mbar_init(B_URDY, 8);
#pragma unroll
    for (int i = 0; i < 16; i++) mbar_init(B_KPART + i * 8, 1);
#pragma unroll
    for (int i = 0; i < 8; i++) { mbar_init(B_KDRDY + i * 8, 1); mbar_init(B_SFREE + i * 8, 1); mbar_init(B_SFULL + i * 8, 1); }
    asm volatile("fence.mbarrier_init.release.cluster;" ::: "memory");
    mbar_expect_tx(B_ULAND, 65536);
#pragma unroll
    for (int i = 0; i < 8; i++) tma2d(sb + CU_OFF + i * 8192, tmU, B_ULAND, ch0, i * 256);
  }
  const int sl = warp & 7, g = lane >> 2, q = lane & 3;
  const bool helper = warp >= NCW;
  KParams kp = load_kparams(P, ch0 + sl, lane);
  const KParams kp2 = load_kparams(P, ch0 + 8 + sl, lane);
  const unsigned tag = load_tag(P.ws);
  const uint32_t wb = sb + CW_OFF + sl * W_BYTES;
  const uint32_t st = wb + (helper ? KST_BYTES : 0);
  __syncthreads();
#pragma unroll 1
  for (int ph = 0; ph < 2; ph++) {
    float kacc[2][3][4];
#pragma unroll
    for (int a = 0; a < 2; a++)
#pragma unroll
      for (int b = 0; b < 3; b++) { kacc[a][b][0] = kacc[a][b][1] = kacc[a][b][2] = kacc[a][b][3] = 0.f; }
    const float dt = bfround(expf(kp.ldt));
#pragma unroll 1
    for (int ps = 0; ps < 2; ps++) kgen_pass(kp, dt, ps + (helper ? 2 : 0), st, kacc);
    kp = kp2;
    if (helper) {
#pragma unroll
      for (int i = 0; i < 24; i++) asm volatile("st.shared.f32 [%0], %1;" ::"r"(wb + W_PART + i * 128 + lane * 4), "f"(kacc[i / 12][(i / 4) % 3][i & 3]) : "memory");
      __syncwarp();
      if (lane == 0) mbar_arrive(B_KPART + (ph * 8 + sl) * 8);
      if (ph == 0) {
        const int ht = tid - NCW * 32;
        uint32_t v[16][4];
        const int m = lane >> 3, r = lane & 7;
        mbar_wait(B_ULAND, 0);
#pragma unroll
        for (int k = 0; k < 16; k++) ldsm4t(v[k], sb + CU_OFF + (sl * 256 + 16 * k + 8 * (m >> 1) + r) * 32 + (m & 1) * 16);
        named_bar(2, 256);
        const uint32_t dst = sb + CU_OFF + (r + 8 * (m & 1)) * U_CH + (m >> 1) * U_HI + (8 + sl * 16) * 16;
#pragma unroll
        for (int k = 0; k < 16; k++)
          asm volatile("stmatrix.sync.aligned.m8n8.x4.shared.b16 [%0], {%1,%2,%3,%4};" ::"r"(dst + k * 16), "r"(v[k][0]), "r"(v[k][1]), "r"(v[k][2]), "r"(v[k][3]) : "memory");
        sts128(sb + CU_OFF + (ht >> 4) * U_CH + ((ht >> 3) & 1) * U_HI + (ht & 7) * 16, make_uint4(0, 0, 0, 0));
        fence_async_smem();
        __syncwarp();
        if (lane == 0) mbar_arrive(B_URDY);
        if (tid == 256) STAMP(16);
        mbar_wait(B_KDRDY + sl * 8, 0);
        if (lane == 0) {
          mbar_wait(B_URDY, 0);
          bulk_s2g(P.ws->uT + (size_t)(cb * 8 + sl) * 4496, sb + CU_OFF + sl * U_CH, 4496);
          bulk_s2g(P.ws->kd + (size_t)(ch0 + sl) * 776, wb + W_KD0, 1552);
          bulk_commit();
          bulk_wait0();
          st_relaxed_u32(&P.ws->kflag[ch0 + sl], tag);
        }
        __syncwarp();
      }
    } else {
      mbar_wait(B_KPART + (ph * 8 + sl) * 8, 0);
      float oth[24];
#pragma unroll
      for (int i = 0; i < 24; i++) oth[i] = __uint_as_float(lds32(wb + W_PART + i * 128 + lane * 4));
      const uint32_t kdb = wb + (ph ? W_KD1 : W_KD0);
#pragma unroll
      for (int i = 0; i < 24; i++) sts16(kdb + kd_slot(i, g, q) * 2, pack_bf16(kacc[i / 12][(i / 4) % 3][i & 3] + oth[i], 0.f) & 0xFFFFu);
      if (lane == 0) sts16(kdb + KD_ZERO * 2, 0);
      if (ph == 0) fence_async_smem();
      __syncwarp();
      if (lane == 0) mbar_arrive((ph ? B_SFREE : B_KDRDY) + sl * 8);
      if (tid == 0) STAMP(1 + ph);
    }
  }
  const uint32_t ub = sb + CU_OFF + (8 + sl) * U_CH;
  if (helper) {
    mbar_wait(B_SFREE + sl * 8, 0);
    build_signals(ub, wb, lane);
    __syncwarp();
    if (lane == 0) mbar_arrive(B_SFULL + sl * 8);
    return;
  }
  build_tables(wb + W_KD1, wb + W_TAB, P.lut, lane);
  mbar_wait(B_URDY, 0);
  if (tid == 0) STAMP(3);
  const int ch = ch0 + 8 + sl;
  conv_channel(ub, wb, wb + W_TAB, B_SFULL + sl * 8, P.ws->y + (size_t)ch * L_, &P.ws->ycnt[(ch / 96) * 32]);
  if (tid == 0) STAMP(4);
}

constexpr int SMEM_BYTES = (S5_SMEM > CONV_SMEM ? S5_SMEM : CONV_SMEM) + 1024;

__global__ void __launch_bounds__(NTHREADS, 1)
fused_kernel(const __grid_constant__ Params P, const __grid_constant__ CUtensorMap tmB, const __grid_constant__ CUtensorMap tmX, const __grid_constant__ CUtensorMap tmU,
             const __grid_constant__ CUtensorMap tmC, const __grid_constant__ CUtensorMap tmY) {
  extern __shared__ unsigned char smem_raw[];
  const uint32_t sb = (smem_u32(smem_raw) + 1023u) & ~1023u;
  const long long t_start = 0;
  unsigned tag0 = 0;
  if (threadIdx.x == 0) tag0 = load_tag(P.ws);
  if (__builtin_expect(blockIdx.x < N_S5, 1)) s5_role(P, &tmX, &tmB, &tmC, &tmY, sb, t_start);
  else conv_role(P, &tmU, sb, t_start);
  if (threadIdx.x == 0) { STAMP(63); }
  __syncthreads();
  if (threadIdx.x == 0) P.ws->epoch[blockIdx.x * 32] = tag0;
}

typedef CUresult (*EncodeFn)(CUtensorMap*, CUtensorMapDataType, cuuint32_t, void*, const cuuint64_t*, const cuuint64_t*, const cuuint32_t*, const cuuint32_t*,
                             CUtensorMapInterleave, CUtensorMapSwizzle, CUtensorMapL2promotion, CUtensorMapFloatOOBfill);

}

extern "C" void kernel_launch(void* const* d_in, const int* in_sizes, int n_in, void* d_out, int out_size) {
  (void)in_sizes; (void)n_in; (void)out_size;
  static EncodeFn enc = nullptr;
  static void* ws_ptr = nullptr;
  static void* lut_ptr = nullptr;
  if (!enc) {
    void* fn = nullptr; cudaDriverEntryPointQueryResult qr;
    cudaGetDriverEntryPoint("cuTensorMapEncodeTiled", &fn, cudaEnableDefault, &qr);
    enc = (EncodeFn)fn;
    cudaGetSymbolAddress(&ws_ptr, g_ws);
    cudaGetSymbolAddress(&lut_ptr, g_lut);
    cudaFuncSetAttribute(fused_kernel, cudaFuncAttributeMaxDynamicSharedMemorySize, SMEM_BYTES);
  }
  typedef const __nv_bfloat16* bp;
  Params P;
  P.u = (bp)d_in[0]; P.logA = (bp)d_in[1]; P.Aim = (bp)d_in[2]; P.Cre = (bp)d_in[3]; P.Cim = (bp)d_in[4]; P.logdtA = (bp)d_in[5]; P.DskA = (bp)d_in[6];
  P.Lre = (bp)d_in[8]; P.Lim = (bp)d_in[9]; P.logdtB = (bp)d_in[14]; P.DskB = (bp)d_in[15]; P.gw = (bp)d_in[16];
  P.out = (float*)d_out;
  P.ws = (Scratch*)ws_ptr; P.lut = (const uint32_t*)lut_ptr;
  void* y_ptr = ((Scratch*)ws_ptr)->y;
  const char* Bre = (const char*)d_in[10]; const char* Bim = (const char*)d_in[11];
  const char* Cre = (const char*)d_in[12]; const char* Cim = (const char*)d_in[13];
  P.swapB = Bim < Bre; P.swapC = Cim < Cre;
  CUtensorMap tmX, tmB, tmC, tmY, tmU;
  const cuuint32_t ones[5] = {1, 1, 1, 1, 1};
  {
    cuuint64_t gd[5] = {576, 2, 4, 16, 16}; cuuint64_t gs[4] = {1152, 32 * 1152, 2 * 1152, 128 * 1152}; cuuint32_t bx[5] = {64, 2, 4, 8, 1};
    enc(&tmX, CU_TENSOR_MAP_DATA_TYPE_BFLOAT16, 5, d_in[0], gd, gs, bx, ones, CU_TENSOR_MAP_INTERLEAVE_NONE, CU_TENSOR_MAP_SWIZZLE_128B, CU_TENSOR_MAP_L2_PROMOTION_L2_128B, CU_TENSOR_MAP_FLOAT_OOB_FILL_NONE);
  }
  {
    cuuint64_t diff = P.swapB ? (cuuint64_t)(Bre - Bim) : (cuuint64_t)(Bim - Bre);
    cuuint64_t gd[4] = {576, 8, 2, 72}; cuuint64_t gs[3] = {1152, diff, 9216}; cuuint32_t bx[4] = {64, 8, 2, 12};
    enc(&tmB, CU_TENSOR_MAP_DATA_TYPE_BFLOAT16, 4, (void*)(P.swapB ? Bim : Bre), gd, gs, bx, ones, CU_TENSOR_MAP_INTERLEAVE_NONE, CU_TENSOR_MAP_SWIZZLE_128B, CU_TENSOR_MAP_L2_PROMOTION_L2_128B, CU_TENSOR_MAP_FLOAT_OOB_FILL_NONE);
  }
  {
    cuuint64_t diff = P.swapC ? (cuuint64_t)(Cre - Cim) : (cuuint64_t)(Cim - Cre);
    cuuint64_t gd[3] = {576, 576, 2}; cuuint64_t gs[2] = {1152, diff}; cuuint32_t bx[3] = {32, 96, 2};
    enc(&tmC, CU_TENSOR_MAP_DATA_TYPE_BFLOAT16, 3, (void*)(P.swapC ? Cim : Cre), gd, gs, bx, ones, CU_TENSOR_MAP_INTERLEAVE_NONE, CU_TENSOR_MAP_SWIZZLE_64B, CU_TENSOR_MAP_L2_PROMOTION_L2_128B, CU_TENSOR_MAP_FLOAT_OOB_FILL_NONE);
  }
  {
    cuuint64_t gd[2] = {2048, 576}; cuuint64_t gs[1] = {4096}; cuuint32_t bx[2] = {64, 96};
    enc(&tmY, CU_TENSOR_MAP_DATA_TYPE_BFLOAT16, 2, y_ptr, gd, gs, bx, ones, CU_TENSOR_MAP_INTERLEAVE_NONE, CU_TENSOR_MAP_SWIZZLE_128B, CU_TENSOR_MAP_L2_PROMOTION_L2_128B, CU_TENSOR_MAP_FLOAT_OOB_FILL_NONE);
  }
  {
    cuuint64_t gd[2] = {576, 2048}; cuuint64_t gs[1] = {1152}; cuuint32_t bx[2] = {16, 256};
    enc(&tmU, CU_TENSOR_MAP_DATA_TYPE_BFLOAT16, 2, d_in[0], gd, gs, bx, ones, CU_TENSOR_MAP_INTERLEAVE_NONE, CU_TENSOR_MAP_SWIZZLE_NONE, CU_TENSOR_MAP_L2_PROMOTION_NONE, CU_TENSOR_MAP_FLOAT_OOB_FILL_NONE);
  }
  cudaLaunchConfig_t cfg = {};
  cfg.gridDim = dim3(N_CTA); cfg.blockDim = dim3(NTHREADS); cfg.dynamicSmemBytes = SMEM_BYTES; cfg.stream = cudaStreamPerThread;
  cudaLaunchAttribute at[1];
  at[0].id = cudaLaunchAttributeClusterDimension; at[0].val.clusterDim.x = 2; at[0].val.clusterDim.y = 1; at[0].val.clusterDim.z = 1;
  cfg.attrs = at; cfg.numAttrs = 1;
  cudaLaunchKernelEx(&cfg, fused_kernel, P, tmB, tmX, tmU, tmC, tmY);
}
```
